```python
import torch

def _softmax(x, axis=-1):
    return torch.softmax(x, dim=axis)
def _gelu(x):
    return torch.nn.functional.gelu(x, approximate="tanh")
def _silu(x):
    return torch.nn.functional.silu(x)
def _sigmoid(x):
    return torch.sigmoid(x)
def _layernorm(x, axis=-1, eps=1e-5):
    m = x.mean(dim=axis, keepdim=True)
    v = x.var(dim=axis, keepdim=True, unbiased=False)
    return (x - m) / torch.sqrt(v + eps)
def _scatter_add(tgt, idx, src, axis=0):
    return tgt.clone().index_add_(axis, idx, src)
def _segment_sum(src, seg, n):
    out = torch.zeros((n,) + src.shape[1:], dtype=src.dtype)
    return out.index_add_(0, seg, src)
def _pad(x, pw):
    flat = tuple(v for pair in reversed(pw) for v in pair)
    return torch.nn.functional.pad(x, flat)

kernel_name = 'gated_mix__linear_attn_block__mha_block__prompt'

def setup_inputs():

    _w = (lambda a: (lambda t: t.to(torch.bfloat16) if t.is_floating_point() else t)(torch.as_tensor(a)))
    def _A_setup():
        B, S, D = 1, 2048, 576
        return {
            "x": _w((lambda *s: torch.randn(*s, dtype=torch.bfloat16) * 0.05)(B, S, D)),
            "wqkv": _w((lambda *s: torch.randn(*s, dtype=torch.bfloat16) * 0.8)(D, 3 * D)),
            "wo": _w((lambda *s: torch.randn(*s, dtype=torch.bfloat16) * 0.2)(D, D)),
        }
    _A_in = _A_setup()

    def _B_setup():
        B, S, D, H = 1, 2048, 576, 32
        return {
            "x": _w((lambda *s: torch.randn(*s, dtype=torch.bfloat16) * 0.05)(B, S, D)),
            "wqkv": _w((lambda *s: torch.randn(*s, dtype=torch.bfloat16) * 0.8)(D, 3 * D)),
            "wo": _w((lambda *s: torch.randn(*s, dtype=torch.bfloat16) * 0.05)(D, D)),
        }
    _B_in = _B_setup()

    return {
        "A_x": _A_in["x"],
        "A_wqkv": _A_in["wqkv"],
        "A_wo": _A_in["wo"],
        "B_x": _B_in["x"],
        "B_wqkv": _B_in["wqkv"],
        "B_wo": _B_in["wo"],
        "gate_w": _w((lambda *s: torch.randn(*s, dtype=torch.bfloat16) * 0.05)(576) * 16.0),
    }

def reference(A_x, A_wqkv, A_wo, B_x, B_wqkv, B_wo, gate_w):
    def _A_ref(x, wqkv, wo):
        B, S, D = x.shape
        H = 32; Dh = D // H
        qkv = (lambda x, *d: x.permute(*d))((x @ wqkv).reshape(B, S, 3, H, Dh), 2, 0, 3, 1, 4)
        q, k, v = qkv[0], qkv[1], qkv[2]
        phi = lambda t: torch.where(t > 0, t + 1, torch.exp(t)) + 1e-6
        pq, pk = phi(q), phi(k)
        kv = torch.einsum("bhsd,bhse->bhde", pk, v)
        z = torch.einsum("bhsd->bhd", pk)
        num = torch.einsum("bhqd,bhde->bhqe", pq, kv)
        den = torch.einsum("bhqd,bhd->bhq", pq, z)[..., None] + 1e-6
        o = num / den
        return (lambda x, *d: x.permute(*d))(o, 0, 2, 1, 3).reshape(B, S, D) @ wo

    def _B_ref(x, wqkv, wo):
        B, S, D = x.shape
        H = 32
        Dh = D // H
        qkv = (lambda x, *d: x.permute(*d))((x @ wqkv).reshape(B, S, 3, H, Dh), 2, 0, 3, 1, 4)
        q, k, v = qkv[0], qkv[1], qkv[2]
        scores = torch.einsum("bhqd,bhkd->bhqk", q, k) * (Dh ** -0.5)
        p = _softmax(scores, axis=-1)
        o = torch.einsum("bhqk,bhkd->bhqd", p, v)
        return (lambda x, *d: x.permute(*d))(o, 0, 2, 1, 3).reshape(B, S, D) @ wo

    x = A_x
    g = _sigmoid((x * gate_w).sum(-1, keepdims=True))
    a = _A_ref(x, A_wqkv, A_wo)
    b = _B_ref(x, B_wqkv, B_wo)
    return g * a + (1 - g) * b
```

```cpp
#include <cuda_runtime.h>
#include <cuda_bf16.h>
#include <cuda.h>
#include <stdint.h>

namespace {

typedef __nv_bfloat16 bf16;

constexpr int S_ = 2048, D_ = 576;
#define PMASK 0xEAu
constexpr uint32_t POLY_MASK = PMASK;
constexpr float QSCALE = 0.23570226039551584f * 1.4426950408889634f;
constexpr float MAGIC = 448.0f;
constexpr float FAST_M_LIMIT = 40.0f;

__device__ __align__(1024) bf16 g_PQ[S_ * D_];
__device__ __align__(1024) uint8_t g_PK[32 * 98304];
__device__ __align__(1024) uint8_t g_VA[32 * 98304];
__device__ __align__(1024) bf16 g_QB[S_ * D_];
__device__ __align__(1024) uint8_t g_KT[32 * 98304];
__device__ __align__(1024) uint8_t g_VT[32 * 98304];
__device__ __align__(1024) float g_NRM[64 * 16];
__device__ __align__(1024) float g_G[S_];
__device__ __align__(1024) bf16 g_C[S_ * 2 * D_];
__device__ __align__(1024) float g_KV[32 * 360];
__device__ __align__(128) unsigned int g_KVFLAG[32];

__device__ __forceinline__ uint32_t smem_u32(const void* p) { return (uint32_t)__cvta_generic_to_shared(p); }

__device__ __forceinline__ void mbar_init(uint32_t bar, uint32_t cnt) {
    asm volatile("mbarrier.init.shared::cta.b64 [%0], %1;" ::"r"(bar), "r"(cnt) : "memory");
}
__device__ __forceinline__ void mbar_expect_tx(uint32_t bar, uint32_t bytes) {
    asm volatile("mbarrier.arrive.expect_tx.shared::cta.b64 _, [%0], %1;" ::"r"(bar), "r"(bytes) : "memory");
}
__device__ __forceinline__ void mbar_arrive_cluster(uint32_t bar, uint32_t cta) {
    asm volatile(
        "{\n.reg .b32 ra;\nmapa.shared::cluster.u32 ra, %0, %1;\n"
        "mbarrier.arrive.shared::cluster.b64 _, [ra];\n}\n" ::"r"(bar), "r"(cta)
        : "memory");
}
__device__ __forceinline__ void mbar_wait(uint32_t bar, uint32_t parity) {
    uint32_t ok;
#pragma unroll 1
    for (uint32_t it = 0; it < (1u << 22); ++it) {
        asm volatile(
            "{\n.reg .pred p;\nmbarrier.try_wait.parity.shared::cta.b64 p, [%1], %2;\nselp.u32 %0, 1, 0, p;\n}\n"
            : "=r"(ok)
            : "r"(bar), "r"(parity)
            : "memory");
        if (ok) return;
    }
    __trap();
}
__device__ __forceinline__ void mbar_wait_cluster(uint32_t bar, uint32_t parity) {
    uint32_t ok;
#pragma unroll 1
    for (uint32_t it = 0; it < (1u << 22); ++it) {
        asm volatile(
            "{\n.reg .pred p;\nmbarrier.try_wait.parity.shared::cta.b64 p, [%1], %2;\nselp.u32 %0, 1, 0, p;\n}\n"
            : "=r"(ok)
            : "r"(bar), "r"(parity)
            : "memory");
        if (ok) return;
    }
    __trap();
}
__device__ __forceinline__ void fence_barrier_init() { asm volatile("fence.mbarrier_init.release.cluster;" ::: "memory"); }
__device__ __forceinline__ void cluster_sync_all() {
    asm volatile("barrier.cluster.arrive.release.aligned;\nbarrier.cluster.wait.acquire.aligned;" ::: "memory");
}
__device__ __forceinline__ void pdl_launch_dependents() { asm volatile("griddepcontrol.launch_dependents;" ::: "memory"); }
__device__ __forceinline__ void pdl_wait() { asm volatile("griddepcontrol.wait;" ::: "memory"); }
__device__ __forceinline__ void named_bar_sync(int id, int n) { asm volatile("bar.sync %0, %1;" ::"r"(id), "r"(n) : "memory"); }

__device__ __forceinline__ void tma_2d(uint32_t dst, const CUtensorMap* tm, int c0, int c1, uint32_t bar) {
    asm volatile(
        "cp.async.bulk.tensor.2d.shared::cluster.global.mbarrier::complete_tx::bytes [%0], [%1, {%3, %4}], [%2];" ::"r"(dst),
        "l"((uint64_t)tm), "r"(bar), "r"(c0), "r"(c1)
        : "memory");
}
__device__ __forceinline__ void tma_2d_mc(uint32_t dst, const CUtensorMap* tm, int c0, int c1, uint32_t bar, uint16_t mask) {
    asm volatile(
        "cp.async.bulk.tensor.2d.shared::cluster.global.mbarrier::complete_tx::bytes.multicast::cluster [%0], [%1, {%3, %4}], [%2], %5;" ::"r"(dst),
        "l"((uint64_t)tm), "r"(bar), "r"(c0), "r"(c1), "h"(mask)
        : "memory");
}
__device__ __forceinline__ void bulk_g2s(uint32_t dst, const void* src, uint32_t bytes, uint32_t bar) {
    asm volatile("cp.async.bulk.shared::cluster.global.mbarrier::complete_tx::bytes [%0], [%1], %2, [%3];" ::"r"(dst),
                 "l"(src), "r"(bytes), "r"(bar)
                 : "memory");
}
__device__ __forceinline__ void prefetch_tmap(const CUtensorMap* tm) {
    asm volatile("prefetch.tensormap [%0];" ::"l"((uint64_t)tm) : "memory");
}

__device__ __forceinline__ uint64_t make_desc(uint32_t addr, uint32_t lbo, uint32_t sbo, uint32_t swz) {
    uint64_t d = 0;
    d |= (uint64_t)((addr & 0x3FFFF) >> 4);
    d |= (uint64_t)((lbo & 0x3FFFF) >> 4) << 16;
    d |= (uint64_t)((sbo & 0x3FFFF) >> 4) << 32;
    d |= (uint64_t)swz << 62;
    return d;
}
__device__ __forceinline__ uint64_t desc_add(uint64_t d, uint32_t off16) {
    const uint32_t lo = (uint32_t)d + off16, hi = (uint32_t)(d >> 32);
    uint64_t r;
    asm("mov.b64 %0, {%1, %2};" : "=l"(r) : "r"(lo), "r"(hi));
    return r;
}
#define WG_FENCE() asm volatile("wgmma.fence.sync.aligned;" ::: "memory")
#define WG_COMMIT() asm volatile("wgmma.commit_group.sync.aligned;" ::: "memory")
#define WG_WAIT(n) asm volatile("wgmma.wait_group.sync.aligned %0;" ::"n"(n) : "memory")

__device__ __forceinline__ void wgmma_ss_n216(float (&d)[108], uint64_t da, uint64_t db, int scaleD) {
    asm volatile("{\n.reg .pred p;\nsetp.ne.b32 p, %110, 0;\n"
        "wgmma.mma_async.sync.aligned.m64n216k16.f32.bf16.bf16 "
        "{%0,%1,%2,%3,%4,%5,%6,%7,%8,%9,%10,%11,%12,%13,%14,%15,%16,%17,%18,%19,%20,%21,%22,%23,%24,%25,%26,%27,%28,%29,%30,%31,%32,%33,%34,%35,%36,%37,%38,%39,%40,%41,%42,%43,%44,%45,%46,%47,%48,%49,%50,%51,%52,%53,%54,%55,%56,%57,%58,%59,%60,%61,%62,%63,%64,%65,%66,%67,%68,%69,%70,%71,%72,%73,%74,%75,%76,%77,%78,%79,%80,%81,%82,%83,%84,%85,%86,%87,%88,%89,%90,%91,%92,%93,%94,%95,%96,%97,%98,%99,%100,%101,%102,%103,%104,%105,%106,%107}, "
        "%108, %109, p, 1, 1, 0, 1;\n}\n"
        : "+f"(d[0]),"+f"(d[1]),"+f"(d[2]),"+f"(d[3]),"+f"(d[4]),"+f"(d[5]),"+f"(d[6]),"+f"(d[7]),"+f"(d[8]),"+f"(d[9]),"+f"(d[10]),"+f"(d[11]),"+f"(d[12]),"+f"(d[13]),"+f"(d[14]),"+f"(d[15]),"+f"(d[16]),"+f"(d[17]),"+f"(d[18]),"+f"(d[19]),"+f"(d[20]),"+f"(d[21]),"+f"(d[22]),"+f"(d[23]),"+f"(d[24]),"+f"(d[25]),"+f"(d[26]),"+f"(d[27]),"+f"(d[28]),"+f"(d[29]),"+f"(d[30]),"+f"(d[31]),"+f"(d[32]),"+f"(d[33]),"+f"(d[34]),"+f"(d[35]),"+f"(d[36]),"+f"(d[37]),"+f"(d[38]),"+f"(d[39]),"+f"(d[40]),"+f"(d[41]),"+f"(d[42]),"+f"(d[43]),"+f"(d[44]),"+f"(d[45]),"+f"(d[46]),"+f"(d[47]),"+f"(d[48]),"+f"(d[49]),"+f"(d[50]),"+f"(d[51]),"+f"(d[52]),"+f"(d[53]),"+f"(d[54]),"+f"(d[55]),"+f"(d[56]),"+f"(d[57]),"+f"(d[58]),"+f"(d[59]),"+f"(d[60]),"+f"(d[61]),"+f"(d[62]),"+f"(d[63]),"+f"(d[64]),"+f"(d[65]),"+f"(d[66]),"+f"(d[67]),"+f"(d[68]),"+f"(d[69]),"+f"(d[70]),"+f"(d[71]),"+f"(d[72]),"+f"(d[73]),"+f"(d[74]),"+f"(d[75]),"+f"(d[76]),"+f"(d[77]),"+f"(d[78]),"+f"(d[79]),"+f"(d[80]),"+f"(d[81]),"+f"(d[82]),"+f"(d[83]),"+f"(d[84]),"+f"(d[85]),"+f"(d[86]),"+f"(d[87]),"+f"(d[88]),"+f"(d[89]),"+f"(d[90]),"+f"(d[91]),"+f"(d[92]),"+f"(d[93]),"+f"(d[94]),"+f"(d[95]),"+f"(d[96]),"+f"(d[97]),"+f"(d[98]),"+f"(d[99]),"+f"(d[100]),"+f"(d[101]),"+f"(d[102]),"+f"(d[103]),"+f"(d[104]),"+f"(d[105]),"+f"(d[106]),"+f"(d[107])
        : "l"(da), "l"(db), "r"(scaleD));
}
__device__ __forceinline__ void wgmma_ss_n64(float (&d)[32], uint64_t da, uint64_t db, int scaleD) {
    asm volatile("{\n.reg .pred p;\nsetp.ne.b32 p, %34, 0;\n"
        "wgmma.mma_async.sync.aligned.m64n64k16.f32.bf16.bf16 "
        "{%0,%1,%2,%3,%4,%5,%6,%7,%8,%9,%10,%11,%12,%13,%14,%15,%16,%17,%18,%19,%20,%21,%22,%23,%24,%25,%26,%27,%28,%29,%30,%31}, "
        "%32, %33, p, 1, 1, 0, 1;\n}\n"
        : "+f"(d[0]),"+f"(d[1]),"+f"(d[2]),"+f"(d[3]),"+f"(d[4]),"+f"(d[5]),"+f"(d[6]),"+f"(d[7]),"+f"(d[8]),"+f"(d[9]),"+f"(d[10]),"+f"(d[11]),"+f"(d[12]),"+f"(d[13]),"+f"(d[14]),"+f"(d[15]),"+f"(d[16]),"+f"(d[17]),"+f"(d[18]),"+f"(d[19]),"+f"(d[20]),"+f"(d[21]),"+f"(d[22]),"+f"(d[23]),"+f"(d[24]),"+f"(d[25]),"+f"(d[26]),"+f"(d[27]),"+f"(d[28]),"+f"(d[29]),"+f"(d[30]),"+f"(d[31])
        : "l"(da), "l"(db), "r"(scaleD));
}
__device__ __forceinline__ void wgmma_ss_n8(float (&d)[4], uint64_t da, uint64_t db, int scaleD) {
    asm volatile("{\n.reg .pred p;\nsetp.ne.b32 p, %6, 0;\n"
        "wgmma.mma_async.sync.aligned.m64n8k16.f32.bf16.bf16 "
        "{%0,%1,%2,%3}, "
        "%4, %5, p, 1, 1, 0, 1;\n}\n"
        : "+f"(d[0]),"+f"(d[1]),"+f"(d[2]),"+f"(d[3])
        : "l"(da), "l"(db), "r"(scaleD));
}
__device__ __forceinline__ void wgmma_rs_n64(float (&d)[32], uint32_t a0, uint32_t a1, uint32_t a2, uint32_t a3, uint64_t db, int scaleD) {
    asm volatile("{\n.reg .pred p;\nsetp.ne.b32 p, %37, 0;\n"
        "wgmma.mma_async.sync.aligned.m64n64k16.f32.bf16.bf16 "
        "{%0,%1,%2,%3,%4,%5,%6,%7,%8,%9,%10,%11,%12,%13,%14,%15,%16,%17,%18,%19,%20,%21,%22,%23,%24,%25,%26,%27,%28,%29,%30,%31}, "
        "{%32,%33,%34,%35}, %36, p, 1, 1, 0;\n}\n"
        : "+f"(d[0]),"+f"(d[1]),"+f"(d[2]),"+f"(d[3]),"+f"(d[4]),"+f"(d[5]),"+f"(d[6]),"+f"(d[7]),"+f"(d[8]),"+f"(d[9]),"+f"(d[10]),"+f"(d[11]),"+f"(d[12]),"+f"(d[13]),"+f"(d[14]),"+f"(d[15]),"+f"(d[16]),"+f"(d[17]),"+f"(d[18]),"+f"(d[19]),"+f"(d[20]),"+f"(d[21]),"+f"(d[22]),"+f"(d[23]),"+f"(d[24]),"+f"(d[25]),"+f"(d[26]),"+f"(d[27]),"+f"(d[28]),"+f"(d[29]),"+f"(d[30]),"+f"(d[31])
        : "r"(a0), "r"(a1), "r"(a2), "r"(a3), "l"(db), "r"(scaleD));
}
__device__ __forceinline__ void wgmma_rs_n24(float (&d)[12], uint32_t a0, uint32_t a1, uint32_t a2, uint32_t a3, uint64_t db, int scaleD) {
    asm volatile("{\n.reg .pred p;\nsetp.ne.b32 p, %17, 0;\n"
        "wgmma.mma_async.sync.aligned.m64n24k16.f32.bf16.bf16 "
        "{%0,%1,%2,%3,%4,%5,%6,%7,%8,%9,%10,%11}, "
        "{%12,%13,%14,%15}, %16, p, 1, 1, 1;\n}\n"
        : "+f"(d[0]),"+f"(d[1]),"+f"(d[2]),"+f"(d[3]),"+f"(d[4]),"+f"(d[5]),"+f"(d[6]),"+f"(d[7]),"+f"(d[8]),"+f"(d[9]),"+f"(d[10]),"+f"(d[11])
        : "r"(a0), "r"(a1), "r"(a2), "r"(a3), "l"(db), "r"(scaleD));
}

__device__ __forceinline__ void mma_16816(float (&d)[4], uint32_t a0, uint32_t a1, uint32_t a2, uint32_t a3, uint32_t b0,
                                          uint32_t b1) {
    asm volatile(
        "mma.sync.aligned.m16n8k16.row.col.f32.bf16.bf16.f32 {%0,%1,%2,%3}, {%4,%5,%6,%7}, {%8,%9}, {%0,%1,%2,%3};"
        : "+f"(d[0]), "+f"(d[1]), "+f"(d[2]), "+f"(d[3])
        : "r"(a0), "r"(a1), "r"(a2), "r"(a3), "r"(b0), "r"(b1));
}

__device__ __forceinline__ uint32_t pack_bf16(float lo, float hi) {
    uint32_t r;
    asm("cvt.rn.bf16x2.f32 %0, %1, %2;" : "=r"(r) : "f"(hi), "f"(lo));
    return r;
}
__device__ __forceinline__ float bf16r(float x) { return __bfloat162float(__float2bfloat16_rn(x)); }
__device__ __forceinline__ float ex2f(float x) {
    float r;
    asm("ex2.approx.ftz.f32 %0, %1;" : "=f"(r) : "f"(x));
    return r;
}
__device__ __forceinline__ float bf_lo(uint32_t w) { return __uint_as_float(w << 16); }
__device__ __forceinline__ float bf_hi(uint32_t w) { return __uint_as_float(w & 0xFFFF0000u); }
__device__ __forceinline__ void stmatrix_x2(uint32_t addr, uint32_t r0, uint32_t r1) {
    asm volatile("stmatrix.sync.aligned.m8n8.x2.shared.b16 [%0], {%1,%2};" ::"r"(addr), "r"(r0), "r"(r1) : "memory");
}
__device__ __forceinline__ uint4 lds128(uint32_t addr) {
    uint4 v;
    asm volatile("ld.shared.v4.u32 {%0,%1,%2,%3}, [%4];" : "=r"(v.x), "=r"(v.y), "=r"(v.z), "=r"(v.w) : "r"(addr) : "memory");
    return v;
}
__device__ __forceinline__ uint32_t ldg32(const void* p) {
    uint32_t v;
    asm volatile("ld.global.u32 %0, [%1];" : "=r"(v) : "l"(p) : "memory");
    return v;
}

constexpr int K1_STAGE = 65536;
constexpr int K1_SMEM = 3 * K1_STAGE + 1024;
constexpr int K1_TX = 32768 + 3 * 8192 + 3072;
constexpr int K1_PITCH = 464;

__device__ __forceinline__ uint32_t lds32(uint32_t addr) {
    uint32_t v;
    asm volatile("ld.shared.u32 %0, [%1];" : "=r"(v) : "r"(addr) : "memory");
    return v;
}
__device__ __forceinline__ uint32_t phi2(uint32_t w) {
    uint32_t mn, mx, r;
    asm("min.bf16x2 %0, %1, %2;" : "=r"(mn) : "r"(w), "r"(0u));
    asm("max.bf16x2 %0, %1, %2;" : "=r"(mx) : "r"(w), "r"(0u));
    const uint32_t e = pack_bf16(ex2f(bf_lo(mn) * 1.4426950408889634f), ex2f(bf_hi(mn) * 1.4426950408889634f));
    asm("add.rn.bf16x2 %0, %1, %2;" : "=r"(r) : "r"(mx), "r"(e));
    asm("add.rn.bf16x2 %0, %1, %2;" : "=r"(r) : "r"(r), "r"(0x35863586u));
    return r;
}

__device__ __forceinline__ void k1_stage(const float (&acc)[108], int qblocks, uint32_t st_addr) {
#pragma unroll
    for (int i = 0; i < 27; i++) {
        const float sc = i < qblocks ? QSCALE : 1.0f;
        stmatrix_x2(st_addr + i * 16, pack_bf16(acc[4 * i] * sc, acc[4 * i + 1] * sc),
                    pack_bf16(acc[4 * i + 2] * sc, acc[4 * i + 3] * sc));
    }
}

__global__ void __cluster_dims__(2, 1, 1) __launch_bounds__(256, 1)
k1_qkv(const __grid_constant__ CUtensorMap tmX, const __grid_constant__ CUtensorMap tmWA,
       const __grid_constant__ CUtensorMap tmWAn, const __grid_constant__ CUtensorMap tmWB,
       const __grid_constant__ CUtensorMap tmWBn, const bf16* __restrict__ x, const bf16* __restrict__ gate_w) {
    extern __shared__ uint8_t smem_raw[];
    __shared__ __align__(8) uint64_t bars[6];
    const uint32_t sb = (smem_u32(smem_raw) + 1023u) & ~1023u;
    const uint32_t bar_full = smem_u32(bars), bar_empty = bar_full + 24;
    const int j = blockIdx.x & 15, rb = blockIdx.x >> 4, crank = blockIdx.x & 1;
    const int branch = j >> 3, jj = j & 7;

    pdl_launch_dependents();
    if (threadIdx.x == 64) prefetch_tmap(&tmX);
    if (threadIdx.x == 96) { prefetch_tmap(branch ? &tmWB : &tmWA); prefetch_tmap(branch ? &tmWBn : &tmWAn); }
    if (blockIdx.x == 0 && threadIdx.x >= 32 && threadIdx.x < 64) g_KVFLAG[threadIdx.x - 32] = 0u;
    if (threadIdx.x == 0) {
        for (int s = 0; s < 3; s++) {
            mbar_init(bar_full + 8 * s, 1);
            mbar_init(bar_empty + 8 * s, 4);
        }
        fence_barrier_init();
    }
    const CUtensorMap* tW = branch ? &tmWB : &tmWA;
    const CUtensorMap* tWn = branch ? &tmWBn : &tmWAn;
    auto issueW = [&](int kb) {
        const int s = kb % 3;
        const uint32_t st = sb + s * K1_STAGE, fb = bar_full + 8 * s;
        mbar_expect_tx(fb, K1_TX);
        tma_2d(st + 32768, tW, jj * 216, kb * 64, fb);
        tma_2d(st + 32768 + 8192, tW, jj * 216 + 64, kb * 64, fb);
        tma_2d(st + 32768 + 16384, tW, jj * 216 + 128, kb * 64, fb);
        tma_2d(st + 32768 + 24576, tWn, jj * 216 + 192, kb * 64, fb);
    };
    auto issueX = [&](int kb) {
        const int s = kb % 3;
        tma_2d_mc(sb + s * K1_STAGE + crank * 16384, &tmX, kb * 64, rb * 256 + crank * 128, bar_full + 8 * s, (uint16_t)3);
    };
    auto issue = [&](int kb) {
        issueW(kb);
        issueX(kb);
    };
    __syncthreads();
    asm volatile("barrier.cluster.arrive.release.aligned;" ::: "memory");
    if (threadIdx.x == 32) {
        issueW(0);
        issueW(1);
        issueW(2);
    }
    __syncwarp();
    asm volatile("barrier.cluster.wait.acquire.aligned;" ::: "memory");
    if (threadIdx.x == 0) {
        issueX(0);
        issueX(1);
        issueX(2);
    }
    {
        const int tid = threadIdx.x, wg = tid >> 7, warp = tid >> 5, lane = tid & 31;

        const int grow = j * 16 + warp * 2;
        const uint32_t goff0 = (uint32_t)grow * 128 + ((((uint32_t)lane >> 2) ^ (grow & 7)) << 4) + (lane & 3) * 4;
        const uint32_t goff1 = (uint32_t)(grow + 1) * 128 + ((((uint32_t)lane >> 2) ^ ((grow + 1) & 7)) << 4) + (lane & 3) * 4;
        const uint32_t* gw = reinterpret_cast<const uint32_t*>(gate_w);
        float gacc0 = 0.f, gacc1 = 0.f;
        float acc0[108], acc1[108];
#pragma unroll
        for (int i = 0; i < 108; i++) acc0[i] = acc1[i] = 0.f;

#pragma unroll 1
        for (int kb = 0; kb < 9; kb++) {
            const int s = kb % 3;
            mbar_wait(bar_full + 8 * s, (kb / 3) & 1);
            const uint32_t st = sb + s * K1_STAGE;
            WG_FENCE();
#pragma unroll
            for (int kk = 0; kk < 4; kk++) {
                uint64_t da0 = make_desc(st + wg * 16384 + kk * 32, 16, 1024, 1);
                uint64_t da1 = make_desc(st + wg * 16384 + 8192 + kk * 32, 16, 1024, 1);
                uint64_t db = make_desc(st + 32768 + kk * 2048, 8192, 1024, 1);
                wgmma_ss_n216(acc0, da0, db, 1);
                wgmma_ss_n216(acc1, da1, db, 1);
            }
            WG_COMMIT();
            {
                const uint32_t b = __ldg(gw + kb * 32 + lane);
                const uint32_t a0 = lds32(st + goff0), a1 = lds32(st + goff1);
                gacc0 += bf16r(bf_lo(a0) * bf_lo(b)) + bf16r(bf_hi(a0) * bf_hi(b));
                gacc1 += bf16r(bf_lo(a1) * bf_lo(b)) + bf16r(bf_hi(a1) * bf_hi(b));
            }
            if (kb >= 1 && kb <= 6) {
                WG_WAIT(1);
                named_bar_sync(2 + wg, 128);
                if ((tid & 127) < 2) mbar_arrive_cluster(bar_empty + 8 * ((kb - 1) % 3), tid & 1);
                if (tid == 0) {
                    mbar_wait_cluster(bar_empty + 8 * ((kb - 1) % 3), ((kb - 1) / 3) & 1);
                    issue(kb + 2);
                }
                __syncwarp();
            }
        }
        {
#pragma unroll
            for (int o = 16; o > 0; o >>= 1) {
                gacc0 += __shfl_xor_sync(0xffffffffu, gacc0, o);
                gacc1 += __shfl_xor_sync(0xffffffffu, gacc1, o);
            }
            if (lane < 2) {
                const float z = bf16r(lane ? gacc1 : gacc0);
                g_G[rb * 256 + grow + lane] = bf16r(1.f / (1.f + __expf(-z)));
            }
        }
        WG_WAIT(0);
        asm volatile("barrier.cluster.arrive.relaxed.aligned;" ::: "memory");
        named_bar_sync(1, 256);

        const int w4 = warp & 3;
        const uint32_t stg = sb + wg * 65536;
        const int c0 = 216 * jj;
        {
            int qb = branch ? (576 - c0) / 8 : 0;
            qb = max(0, min(27, qb));
            const uint32_t st_addr = stg + (uint32_t)(w4 * 16 + (lane & 15)) * K1_PITCH;
            k1_stage(acc0, qb, st_addr);
            k1_stage(acc1, qb, st_addr + 64 * K1_PITCH);
        }
        named_bar_sync(2 + wg, 128);

        const int rowbase = rb * 256 + wg * 128;
        const int nnat = max(0, min(27, (576 - c0) / 8));
        const int r8 = lane & 7, c4 = lane >> 3;
        if (nnat > 0) {
            uint8_t* dst = reinterpret_cast<uint8_t*>(branch ? g_QB : g_PQ) + (size_t)(rowbase >> 3) * 9216 + (c0 >> 3) * 128 + r8 * 16;
#pragma unroll 1
            for (int qi = w4 * 4 + c4; qi < nnat * 4; qi += 16) {
                const int rq4 = qi / nnat, i = qi - rq4 * nnat, rg0 = rq4 * 4;
#pragma unroll
                for (int rr = 0; rr < 4; rr++) {
                    const int rg = rg0 + rr;
                    uint4 v = lds128(stg + (rg * 8 + r8) * K1_PITCH + i * 16);
                    if (branch == 0) {
                        v.x = phi2(v.x); v.y = phi2(v.y); v.z = phi2(v.z); v.w = phi2(v.w);
                    }
                    *reinterpret_cast<uint4*>(dst + (size_t)rg * 9216 + i * 128) = v;
                }
            }
        }
        {
            const int u0 = nnat * 8 / 18;
            const int nflat = (12 - u0) * 3;
#pragma unroll 1
            for (int qi = w4 * 4 + c4; qi < nflat * 4; qi += 16) {
                const int rq4 = qi / nflat, f = qi - rq4 * nflat, rg0 = rq4 * 4;
                const int uu = f / 3, ch = f - uu * 3;
                const int u = u0 + uu;
                const int gcol = c0 + 18 * u;
                const int type = gcol >= 1152 ? 2 : 1;
                const int head = (gcol - 576 * type) / 18;
                uint8_t* gimg = branch ? (type == 1 ? g_KT : g_VT) : (type == 1 ? g_PK : g_VA);
                uint8_t* gdst = gimg + (size_t)head * 98304 + (size_t)(rowbase >> 3) * 384 + ch * 128 + r8 * 16;
                const uint32_t sa = stg + r8 * K1_PITCH + u * 36 + ch * 16;
                const bool dophi = (branch == 0 && type == 1);
#pragma unroll
                for (int rr = 0; rr < 4; rr++) {
                    const int rg = rg0 + rr;
                    uint4 v;
                    v.x = lds32(sa + rg * 8 * K1_PITCH);
                    v.y = lds32(sa + rg * 8 * K1_PITCH + 4);
                    v.z = lds32(sa + rg * 8 * K1_PITCH + 8);
                    v.w = lds32(sa + rg * 8 * K1_PITCH + 12);
                    if (dophi) { v.x = phi2(v.x); v.y = phi2(v.y); v.z = phi2(v.z); v.w = phi2(v.w); }
                    if (ch == 2) {
                        v.y = (type == 2 || ((POLY_MASK >> (rg & 7)) & 1)) ? 0x00003F80u : 0x3F800000u;
                        v.z = 0u;
                        v.w = 0u;
                    }
                    *reinterpret_cast<uint4*>(gdst + rg * 384) = v;
                }
            }
        }
        if (branch) {
            const int u = w4 * 3 + c4;
            const bool act = c4 < 3 && (c0 + 18 * u) < 1152;
            uint32_t mx = 0;
            if (act) {
                const uint32_t sa = stg + r8 * K1_PITCH + u * 36;
#pragma unroll 2
                for (int rg = 0; rg < 16; rg++) {
                    float ss = 0.f;
#pragma unroll
                    for (int k = 0; k < 9; k++) {
                        const uint32_t w = lds32(sa + rg * 8 * K1_PITCH + 4 * k);
                        ss = fmaf(bf_lo(w), bf_lo(w), ss);
                        ss = fmaf(bf_hi(w), bf_hi(w), ss);
                    }
                    mx = max(mx, __float_as_uint(ss) & 0x7FFFFFFFu);
                }
            }
            mx = max(mx, __shfl_xor_sync(0xffffffffu, mx, 1));
            mx = max(mx, __shfl_xor_sync(0xffffffffu, mx, 2));
            mx = max(mx, __shfl_xor_sync(0xffffffffu, mx, 4));
            if (act && r8 == 0) g_NRM[((c0 + 18 * u) / 18) * 16 + rb * 2 + wg] = __uint_as_float(mx);
        }
        asm volatile("barrier.cluster.wait.aligned;" ::: "memory");
    }
}

constexpr int K2_SMEM = 196608 + 1024 + 16 * 360 * 4 + 1024;

__device__ __forceinline__ uint32_t exp2_pair(float t0, float t1) {
    uint32_t H, y, c, r;
    asm("prmt.b32 %0, %1, %2, 0x6521;" : "=r"(H) : "r"(__float_as_uint(t0)), "r"(__float_as_uint(t1)));
    asm("lop3.b32 %0, %1, 0x007F007F, 0x3F803F80, 0xEA;" : "=r"(y) : "r"(H));
    asm("fma.rn.bf16x2 %0, %1, %2, %3;" : "=r"(c) : "r"(0x9DE89DE8u), "r"(y), "r"(0x1EAB1EABu));
    asm("fma.rn.bf16x2 %0, %1, %2, %3;" : "=r"(c) : "r"(c), "r"(y), "r"(0x9F389F38u));
    asm("mul.rn.bf16x2 %0, %1, %2;" : "=r"(r) : "r"(H), "r"(c));
    return r;
}
__device__ __forceinline__ void softmax64(const float (&s)[32], uint32_t (&p)[16]) {
#pragma unroll
    for (int b = 0; b < 8; b++) {
        if ((POLY_MASK >> b) & 1) {
            p[2 * b] = exp2_pair(s[4 * b], s[4 * b + 1]);
            p[2 * b + 1] = exp2_pair(s[4 * b + 2], s[4 * b + 3]);
        } else {
            p[2 * b] = pack_bf16(ex2f(s[4 * b]), ex2f(s[4 * b + 1]));
            p[2 * b + 1] = pack_bf16(ex2f(s[4 * b + 2]), ex2f(s[4 * b + 3]));
        }
    }
}

__device__ __forceinline__ void ldsm_x4_t(uint32_t addr, uint32_t& r0, uint32_t& r1, uint32_t& r2, uint32_t& r3) {
    asm volatile("ldmatrix.sync.aligned.m8n8.x4.trans.shared.b16 {%0,%1,%2,%3}, [%4];"
                 : "=r"(r0), "=r"(r1), "=r"(r2), "=r"(r3) : "r"(addr) : "memory");
}
__device__ __forceinline__ void ldsm_x2_t(uint32_t addr, uint32_t& r0, uint32_t& r1) {
    asm volatile("ldmatrix.sync.aligned.m8n8.x2.trans.shared.b16 {%0,%1}, [%2];" : "=r"(r0), "=r"(r1) : "r"(addr) : "memory");
}
__device__ __forceinline__ void kv_cta(uint8_t* sptr, uint32_t sb, int cta, int tid) {
    const int warp = tid >> 5, lane = tid & 31, g = lane >> 2, t = lane & 3;
    const uint32_t sBar = sb + 196608;
    float* part = reinterpret_cast<float*>(sptr + 196608 + 1024);
    auto issue = [&](int it) {
        const int st = it & 3, h = cta * 8 + (it >> 2);
        mbar_expect_tx(sBar + 8 * st, 49152);
        bulk_g2s(sb + st * 49152, g_PK + (size_t)h * 98304 + st * 24576, 24576, sBar + 8 * st);
        bulk_g2s(sb + st * 49152 + 24576, g_VA + (size_t)h * 98304 + st * 24576, 24576, sBar + 8 * st);
    };
    if (tid == 0) { issue(0); issue(1); issue(2); issue(3); }
    const uint32_t o4 = warp * 4 * 384 + (lane >> 4) * 384 + ((lane >> 3) & 1) * 128 + (lane & 7) * 16;
    const uint32_t o2 = warp * 4 * 384 + ((lane >> 3) & 1) * 384 + 256 + (lane & 7) * 16;
#pragma unroll 1
    for (int hh = 0; hh < 8; hh++) {
        float d[2][3][4];
#pragma unroll
        for (int a = 0; a < 2; a++)
#pragma unroll
            for (int b = 0; b < 3; b++)
#pragma unroll
                for (int c = 0; c < 4; c++) d[a][b][c] = 0.f;
#pragma unroll 1
        for (int qt = 0; qt < 4; qt++) {
            mbar_wait(sBar + 8 * qt, hh & 1);
            const uint32_t pk = sb + qt * 49152, va = pk + 24576;
#pragma unroll
            for (int ks = 0; ks < 2; ks++) {
                uint32_t a0, a1, a2, a3, c0, c2, b00, b10, b01, b11, b20, b21;
                ldsm_x4_t(pk + ks * 768 + o4, a0, a1, a2, a3);
                ldsm_x2_t(pk + ks * 768 + o2, c0, c2);
                ldsm_x4_t(va + ks * 768 + o4, b00, b10, b01, b11);
                ldsm_x2_t(va + ks * 768 + o2, b20, b21);
                mma_16816(d[0][0], a0, a1, a2, a3, b00, b01);
                mma_16816(d[0][1], a0, a1, a2, a3, b10, b11);
                mma_16816(d[0][2], a0, a1, a2, a3, b20, b21);
                mma_16816(d[1][0], c0, 0u, c2, 0u, b00, b01);
                mma_16816(d[1][1], c0, 0u, c2, 0u, b10, b11);
                mma_16816(d[1][2], c0, 0u, c2, 0u, b20, b21);
            }
            __syncthreads();
            if (tid == 0 && hh < 7) issue(4 * (hh + 1) + qt);
        }
        float* pw = part + warp * 360;
#pragma unroll
        for (int nt = 0; nt < 3; nt++) {
            if (nt < 2 || t < 2) {
                *reinterpret_cast<float2*>(pw + g * 20 + 8 * nt + 2 * t) = make_float2(d[0][nt][0], d[0][nt][1]);
                *reinterpret_cast<float2*>(pw + (g + 8) * 20 + 8 * nt + 2 * t) = make_float2(d[0][nt][2], d[0][nt][3]);
                if (g < 2) *reinterpret_cast<float2*>(pw + (16 + g) * 20 + 8 * nt + 2 * t) = make_float2(d[1][nt][0], d[1][nt][1]);
            }
        }
        __syncthreads();
        if (tid < 360) {
            float a = 0.f;
#pragma unroll
            for (int w = 0; w < 16; w++) a += part[w * 360 + tid];
            g_KV[(cta * 8 + hh) * 360 + tid] = a;
        }
        __syncthreads();
        if (tid == 0) {
            __threadfence();
            asm volatile("st.release.gpu.global.u32 [%0], %1;" ::"l"(g_KVFLAG + cta * 8 + hh), "r"(1u) : "memory");
        }
    }
}

__device__ __forceinline__ uint32_t q_word(const bf16* img, int row, int col) {
    return ldg32(reinterpret_cast<const uint8_t*>(img) + (size_t)(row >> 3) * 9216 + (col >> 3) * 128 + (row & 7) * 16 + (col & 7) * 2);
}
__device__ __forceinline__ uint8_t* c_img(int row, int k) {
    return reinterpret_cast<uint8_t*>(g_C) + (size_t)(row >> 3) * 18432 + (k >> 3) * 128 + (row & 7) * 16 + (k & 7) * 2;
}
__device__ __forceinline__ void fetch_kv(float* kvs, uint32_t bar, int h, int lane) {
    uint32_t f = 0;
#pragma unroll 1
    for (uint32_t it = 0; it < (1u << 24); ++it) {
        asm volatile("ld.acquire.gpu.global.u32 %0, [%1];" : "=r"(f) : "l"(g_KVFLAG + h) : "memory");
        if (f) break;
        __nanosleep(64);
    }
    if (!f) __trap();
    uint32_t v[12];
#pragma unroll
    for (int i = 0; i < 12; i++) v[i] = (i * 32 + lane) < 360 ? ldg32(g_KV + h * 360 + i * 32 + lane) : 0u;
#pragma unroll
    for (int i = 0; i < 12; i++)
        if ((i * 32 + lane) < 360) kvs[i * 32 + lane] = __uint_as_float(v[i]);
    __syncwarp();
    if (lane == 0) asm volatile("mbarrier.arrive.shared::cta.b64 _, [%0];" ::"r"(bar) : "memory");
}

struct LinIn {
    uint32_t aq[2][6];
    float gg[2][2];
};
__device__ __forceinline__ void linear_load(LinIn& in, int h, int row0, int lane) {
    const int g = lane >> 2, t = lane & 3;
#pragma unroll
    for (int ps = 0; ps < 2; ps++) {
        const int rowA = row0 + ps * 256 + g;
        const int cb = h * 18;
        in.aq[ps][0] = q_word(g_PQ, rowA, cb + 2 * t); in.aq[ps][1] = q_word(g_PQ, rowA + 8, cb + 2 * t);
        in.aq[ps][2] = q_word(g_PQ, rowA, cb + 8 + 2 * t); in.aq[ps][3] = q_word(g_PQ, rowA + 8, cb + 8 + 2 * t);
        in.aq[ps][4] = q_word(g_PQ, rowA, cb + 16); in.aq[ps][5] = q_word(g_PQ, rowA + 8, cb + 16);
        in.gg[ps][0] = __uint_as_float(ldg32(g_G + rowA)); in.gg[ps][1] = __uint_as_float(ldg32(g_G + rowA + 8));
    }
}
__device__ __forceinline__ void linear_apply(const LinIn& in, const float* kv, int h, int row0, int lane, bool live) {
    const int g = lane >> 2, t = lane & 3;
    uint32_t bk[3][3];
#pragma unroll
    for (int nt = 0; nt < 3; nt++) {
        const int e = 8 * nt + g;
        bk[nt][0] = bk[nt][1] = bk[nt][2] = 0u;
        if (e < 19) {
            bk[nt][0] = pack_bf16(kv[(2 * t) * 20 + e], kv[(2 * t + 1) * 20 + e]);
            bk[nt][1] = pack_bf16(kv[(2 * t + 8) * 20 + e], kv[(2 * t + 9) * 20 + e]);
            if (t == 0) bk[nt][2] = pack_bf16(kv[16 * 20 + e], kv[17 * 20 + e]);
        }
    }
#pragma unroll
    for (int ps = 0; ps < 2; ps++) {
        const int rowA = row0 + ps * 256 + g;
        float n[3][4];
        const uint32_t c0 = t == 0 ? in.aq[ps][4] : 0u, c1 = t == 0 ? in.aq[ps][5] : 0u;
#pragma unroll
        for (int nt = 0; nt < 3; nt++) {
            n[nt][0] = n[nt][1] = n[nt][2] = n[nt][3] = 0.f;
            mma_16816(n[nt], in.aq[ps][0], in.aq[ps][1], in.aq[ps][2], in.aq[ps][3], bk[nt][0], bk[nt][1]);
            mma_16816(n[nt], c0, c1, 0u, 0u, bk[nt][2], 0u);
        }
        const int src = (lane & ~3) | 1;
        float dn0 = __shfl_sync(0xffffffffu, n[2][0], src), dn1 = __shfl_sync(0xffffffffu, n[2][2], src);
        dn0 = bf16r(bf16r(dn0) + 1e-6f);
        dn1 = bf16r(bf16r(dn1) + 1e-6f);
        const float sa0 = in.gg[ps][0] / dn0, sa1 = in.gg[ps][1] / dn1;
        uint8_t* cp = c_img(rowA, h * 18 + 2 * t);
#pragma unroll
        for (int nt = 0; nt < 3; nt++) {
            if (live && (nt < 2 || t == 0)) {
                *reinterpret_cast<uint32_t*>(cp + 128 * nt) = pack_bf16(n[nt][0] * sa0, n[nt][1] * sa0);
                *reinterpret_cast<uint32_t*>(cp + 18432 + 128 * nt) = pack_bf16(n[nt][2] * sa1, n[nt][3] * sa1);
            }
        }
    }
}

__global__ void __cluster_dims__(2, 1, 1) __launch_bounds__(512, 1) k2_attn(const bf16* __restrict__ woA, const bf16* __restrict__ woB) {
    extern __shared__ uint8_t smem_raw[];
    const uint32_t sb = (smem_u32(smem_raw) + 1023u) & ~1023u;
    const uint32_t sK = sb, sV = sb + 98304, sBar = sb + 196608;
    const int tid = threadIdx.x, wg = tid >> 7, warp = tid >> 5, lane = tid & 31;
    const int g = lane >> 2, t = lane & 3, w4 = warp & 3;
    pdl_launch_dependents();

    if (tid == 0) {
        for (int c = 0; c < 17; c++) mbar_init(sBar + 8 * c, 1);
        fence_barrier_init();
    }
    cluster_sync_all();
    if (blockIdx.x < 4) {
        if (tid < 18) {
            const uint8_t* w = reinterpret_cast<const uint8_t*>((blockIdx.x & 1) ? woB : woA) + ((blockIdx.x >> 1) * 18 + tid) * 18432;
            asm volatile("cp.async.bulk.prefetch.L2.global [%0], %1;" ::"l"(w), "r"(18432) : "memory");
        }
        pdl_wait();
        kv_cta(smem_raw + (sb - smem_u32(smem_raw)), sb, blockIdx.x, tid);
        return;
    }
    const int h = (blockIdx.x - 4) >> 2, rq = (blockIdx.x - 4) & 3;
    float* kvs = reinterpret_cast<float*>(smem_raw + (sb - smem_u32(smem_raw)) + 196608 + 1024);
    const uint64_t dK0 = make_desc(sK, 128, 384, 0), dK1 = make_desc(sK + 256, 0, 384, 0), dV0 = make_desc(sV, 384, 128, 0);
    bool fast = true;
    uint32_t auxw = 0u;

#pragma unroll 1
    for (int pass = 0; pass < 2; pass++) {
        const bool live = true;
        if (pass == 0) {
            pdl_wait();
            if (lane == 0) {
                const uint8_t* gsrc = ((blockIdx.x & 1) ? g_VT : g_KT) + (size_t)h * 98304;
                const uint32_t sdst = (blockIdx.x & 1) ? sV : sK;
                mbar_expect_tx(sBar + 8 * warp, 12288);
                asm volatile(
                    "cp.async.bulk.shared::cluster.global.mbarrier::complete_tx::bytes.multicast::cluster [%0], [%1], %2, [%3], %4;" ::"r"(
                        sdst + warp * 6144),
                    "l"(gsrc + warp * 6144), "r"(6144), "r"(sBar + 8 * warp), "h"((uint16_t)3)
                    : "memory");
            }
            __syncwarp();
        }
        const int rowA = rq * 512 + (max(pass, 0) * 4 + wg) * 64 + w4 * 16 + g;
        uint32_t qa[8];
        {
            const int cb = h * 18;
            qa[0] = q_word(g_QB, rowA, cb + 2 * t);
            qa[1] = q_word(g_QB, rowA + 8, cb + 2 * t);
            qa[2] = q_word(g_QB, rowA, cb + 8 + 2 * t);
            qa[3] = q_word(g_QB, rowA + 8, cb + 8 + 2 * t);
            qa[4] = q_word(g_QB, rowA, cb + 16);
            qa[5] = q_word(g_QB, rowA + 8, cb + 16);
            qa[6] = 0u;
            qa[7] = 0u;
        }
        const float g0 = __uint_as_float(ldg32(g_G + rowA)), g1 = __uint_as_float(ldg32(g_G + rowA + 8));
        if (pass <= 0) {
            uint32_t nq = ldg32(g_NRM + h * 16 + (lane & 15));
            uint32_t nk = ldg32(g_NRM + (32 + h) * 16 + (lane & 15));
            nq = __reduce_max_sync(0xffffffffu, nq);
            nk = __reduce_max_sync(0xffffffffu, nk);
            const float bound = sqrtf(__uint_as_float(nq)) * sqrtf(__uint_as_float(nk)) * 1.001f;
            const float Mb = 2.f * ceilf(bound * 0.5f);
            fast = (Mb <= FAST_M_LIMIT) || !live;
            auxw = fast ? pack_bf16(MAGIC - Mb, -Mb) : 0u;
        }
        qa[4] = t == 0 ? qa[4] : (t == 1 ? auxw : 0u);
        qa[5] = t == 0 ? qa[5] : (t == 1 ? auxw : 0u);
        float o[12], o2[12];
#pragma unroll
        for (int i = 0; i < 12; i++) o[i] = o2[i] = 0.f;
        if (fast) {
            const int nq4 = live ? 8 : 1, nc = live ? 2 : 1;
#pragma unroll 1
            for (int q4 = 0; q4 < nq4; q4++) {
                if (pass == 0) {
                    mbar_wait(sBar + 16 * q4, 0);
                    mbar_wait(sBar + 16 * q4 + 8, 0);
                } else if (q4 == 6 && warp == 15) {
                    fetch_kv(kvs, sBar + 128, h, lane);
                }
                float s[32];
                uint32_t p[16];
#pragma unroll 1
                for (int c = 2 * q4; c < 2 * q4 + nc; c++) {
#pragma unroll
                    for (int hf = 0; hf < 2; hf++) {
                        const uint32_t off = (uint32_t)(c * 2 + hf) * 192u;
                        WG_FENCE();
                        wgmma_rs_n64(s, qa[0], qa[1], qa[2], qa[3], desc_add(dK0, off), 0);
                        wgmma_rs_n64(s, qa[4], qa[5], qa[6], qa[7], desc_add(dK1, off), 1);
                        WG_COMMIT();
                        WG_WAIT(0);
                        softmax64(s, p);
                        WG_FENCE();
                        wgmma_rs_n24(o, p[0], p[1], p[2], p[3], desc_add(dV0, off), 1);
                        wgmma_rs_n24(o2, p[4], p[5], p[6], p[7], desc_add(dV0, off + 48u), 1);
                        wgmma_rs_n24(o, p[8], p[9], p[10], p[11], desc_add(dV0, off + 96u), 1);
                        wgmma_rs_n24(o2, p[12], p[13], p[14], p[15], desc_add(dV0, off + 144u), 1);
                        WG_COMMIT();
                    }
                }
                WG_WAIT(0);
            }
        } else {
            float m0 = -INFINITY, m1 = -INFINITY;
            float s[32];
            uint32_t p[16];
#pragma unroll 1
            for (int kt = 0; kt < 32; kt++) {
                if (pass == 0 && (kt & 1) == 0) mbar_wait(sBar + 8 * (kt >> 1), 0);
                const uint32_t off = (uint32_t)kt * 192u;
                WG_FENCE();
                wgmma_rs_n64(s, qa[0], qa[1], qa[2], qa[3], desc_add(dK0, off), 0);
                wgmma_rs_n64(s, qa[4], qa[5], qa[6], qa[7], desc_add(dK1, off), 1);
                WG_COMMIT();
                WG_WAIT(0);
                float x0 = s[0], x1 = s[2];
#pragma unroll
                for (int b = 0; b < 8; b++) {
                    x0 = fmaxf(x0, fmaxf(s[4 * b], s[4 * b + 1]));
                    x1 = fmaxf(x1, fmaxf(s[4 * b + 2], s[4 * b + 3]));
                }
                x0 = fmaxf(x0, __shfl_xor_sync(0xffffffffu, x0, 1));
                x1 = fmaxf(x1, __shfl_xor_sync(0xffffffffu, x1, 1));
                x0 = fmaxf(x0, __shfl_xor_sync(0xffffffffu, x0, 2));
                x1 = fmaxf(x1, __shfl_xor_sync(0xffffffffu, x1, 2));
                const float n0 = fmaxf(m0, x0), n1 = fmaxf(m1, x1);
                const float al0 = ex2f(m0 - n0), al1 = ex2f(m1 - n1);
                m0 = n0;
                m1 = n1;
#pragma unroll
                for (int b = 0; b < 3; b++) {
                    o[4 * b] *= al0; o[4 * b + 1] *= al0; o[4 * b + 2] *= al1; o[4 * b + 3] *= al1;
                }
#pragma unroll
                for (int b = 0; b < 8; b++) {
                    p[2 * b] = pack_bf16(ex2f(s[4 * b] - n0), ex2f(s[4 * b + 1] - n0));
                    p[2 * b + 1] = pack_bf16(ex2f(s[4 * b + 2] - n1), ex2f(s[4 * b + 3] - n1));
                }
                WG_FENCE();
#pragma unroll
                for (int kk = 0; kk < 4; kk++)
                    wgmma_rs_n24(o, p[4 * kk], p[4 * kk + 1], p[4 * kk + 2], p[4 * kk + 3], desc_add(dV0, off + kk * 48u), 1);
                WG_COMMIT();
                WG_WAIT(0);
            }
        }
        LinIn lin;
        if (pass != 0) linear_load(lin, h, rq * 512 + wg * 64 + w4 * 16, lane);

        {
#pragma unroll
            for (int i = 0; i < 12; i++) o[i] += o2[i];
            const int src = (lane & ~3) | 1;
            const float l0 = __shfl_sync(0xffffffffu, o[8], src), l1 = __shfl_sync(0xffffffffu, o[10], src);
            const float sb0 = bf16r(1.f - g0) / l0, sb1 = bf16r(1.f - g1) / l1;
            uint8_t* cp = c_img(rowA, 576 + h * 18 + 2 * t);
#pragma unroll
            for (int nt = 0; nt < 3; nt++) {
                if (live && (nt < 2 || t == 0)) {
                    *reinterpret_cast<uint32_t*>(cp + 128 * nt) = pack_bf16(o[4 * nt] * sb0, o[4 * nt + 1] * sb0);
                    *reinterpret_cast<uint32_t*>(cp + 18432 + 128 * nt) = pack_bf16(o[4 * nt + 2] * sb1, o[4 * nt + 3] * sb1);
                }
            }
        }
        if (pass != 0) {
            if (live) {
                if (!fast && warp == 15) fetch_kv(kvs, sBar + 128, h, lane);
                mbar_wait(sBar + 128, 0);
            }
            linear_apply(lin, kvs, h, rq * 512 + wg * 64 + w4 * 16, lane, live);
        }
    }
}

constexpr int K3_STAGE = 24576;
constexpr int K3_NST = 9;
constexpr int K3_SMEM = K3_NST * (K3_STAGE + 1024) + 1024;
constexpr int K3_TX = 16384 + 8192 + 1024;
constexpr int K3_PITCH = 160;

__global__ void __cluster_dims__(2, 1, 1) __launch_bounds__(576, 1)
k3_out(const __grid_constant__ CUtensorMap tmC, const __grid_constant__ CUtensorMap tmOA,
       const __grid_constant__ CUtensorMap tmOAn, const __grid_constant__ CUtensorMap tmOB,
       const __grid_constant__ CUtensorMap tmOBn, bf16* __restrict__ out) {
    extern __shared__ uint8_t smem_raw[];
    __shared__ __align__(8) uint64_t bars[2 * K3_NST];
    const uint32_t sb = (smem_u32(smem_raw) + 1023u) & ~1023u;
    uint8_t* sptr = smem_raw + (sb - smem_u32(smem_raw));
    const uint32_t bar_full = smem_u32(bars), bar_empty = bar_full + 8 * K3_NST;
    const int tid = threadIdx.x, wg = tid >> 7, warp = tid >> 5, lane = tid & 31;
    const int nj = blockIdx.x & 7, rb = blockIdx.x >> 3, crank = blockIdx.x & 1;

    if (tid == 0) {
        for (int s = 0; s < K3_NST; s++) {
            mbar_init(bar_full + 8 * s, 1);
            mbar_init(bar_empty + 8 * s, 4);
        }
        fence_barrier_init();
    }
    cluster_sync_all();

    if (wg == 4) {
        if (lane == 0) {
            if (warp == 16) {
#pragma unroll 1
                for (int l = 0; l < 18; l++) {
                    const int s = l % K3_NST, kb = l >> 1, kh = l & 1;
                    if (l >= K3_NST) mbar_wait(bar_empty + 8 * s, ((l / K3_NST) - 1) & 1);
                    const uint32_t st = sb + s * K3_STAGE, fb = bar_full + 8 * s;
                    mbar_expect_tx(fb, K3_TX);
                    tma_2d(st + 16384, kh ? &tmOB : &tmOA, nj * 72, kb * 64, fb);
                    tma_2d(sb + K3_NST * K3_STAGE + s * 1024, kh ? &tmOBn : &tmOAn, nj * 72 + 64, kb * 64, fb);
                }
            } else {
                prefetch_tmap(&tmC);
                pdl_wait();
#pragma unroll 1
                for (int l = 0; l < 18; l++) {
                    const int s = l % K3_NST, kb = l >> 1, kh = l & 1;
                    if (l >= K3_NST) mbar_wait(bar_empty + 8 * s, ((l / K3_NST) - 1) & 1);
                    tma_2d_mc(sb + s * K3_STAGE + crank * 8192, &tmC, (kh * 9 + kb) * 256, rb * 16 + crank * 8, bar_full + 8 * s, (uint16_t)3);
                }
            }
        }
        __syncwarp();
        asm volatile("barrier.cluster.arrive.relaxed.aligned;\nbarrier.cluster.wait.aligned;" ::: "memory");
        return;
    }
    const int mh = wg & 1, kh = wg >> 1;
    float acc[36];
    float (&accm)[32] = *reinterpret_cast<float(*)[32]>(&acc[0]);
    float (&accn)[4] = *reinterpret_cast<float(*)[4]>(&acc[32]);
#pragma unroll
    for (int i = 0; i < 36; i++) acc[i] = 0.f;

#pragma unroll 1
    for (int kb = 0; kb < 9; kb++) {
        const int l = 2 * kb + kh, s = l % K3_NST;
        mbar_wait(bar_full + 8 * s, (l / K3_NST) & 1);
        const uint32_t st = sb + s * K3_STAGE;
        WG_FENCE();
#pragma unroll
        for (int kk = 0; kk < 4; kk++) {
            uint64_t da = make_desc(st + mh * 8192 + kk * 256, 128, 1024, 0);
            uint64_t db = make_desc(st + 16384 + kk * 2048, 8192, 1024, 1);
            uint64_t dn = make_desc(sb + K3_NST * K3_STAGE + s * 1024 + kk * 256, 128, 128, 0);
            wgmma_ss_n64(accm, da, db, 1);
            wgmma_ss_n8(accn, da, dn, 1);
        }
        WG_COMMIT();
        WG_WAIT(0);
        if (l + K3_NST < 18) {
            if ((tid & 127) < 2) mbar_arrive_cluster(bar_empty + 8 * s, tid & 1);
            __syncwarp();
        }
    }
    asm volatile("barrier.cluster.arrive.relaxed.aligned;" ::: "memory");

    const int g = lane >> 2, t = lane & 3, w4 = warp & 3, tw = tid & 127;
    named_bar_sync(1, 512);
    float* red = reinterpret_cast<float*>(sptr) + (mh * 2 + kh) * (20 * 128);
    float* red_peer = reinterpret_cast<float*>(sptr) + (mh * 2 + (kh ^ 1)) * (20 * 128);
    if (kh == 0) {
#pragma unroll
        for (int i = 0; i < 16; i++) red[i * 128 + tw] = acc[20 + i];
    } else {
#pragma unroll
        for (int i = 0; i < 20; i++) red[i * 128 + tw] = acc[i];
    }
    named_bar_sync(2 + mh, 256);
    (void)g; (void)t;
    const uint32_t stg = sb + 65536 + mh * 16384;
    const uint32_t st_addr = stg + (uint32_t)(w4 * 16 + (lane & 15)) * K3_PITCH;
    if (kh == 0) {
#pragma unroll
        for (int b = 0; b < 5; b++) {
            const float v0 = acc[4 * b] + red_peer[(4 * b) * 128 + tw], v1 = acc[4 * b + 1] + red_peer[(4 * b + 1) * 128 + tw];
            const float v2 = acc[4 * b + 2] + red_peer[(4 * b + 2) * 128 + tw], v3 = acc[4 * b + 3] + red_peer[(4 * b + 3) * 128 + tw];
            stmatrix_x2(st_addr + b * 16, pack_bf16(v0, v1), pack_bf16(v2, v3));
        }
    } else {
#pragma unroll
        for (int b = 5; b < 9; b++) {
            const int r = 4 * (b - 5);
            const float v0 = acc[4 * b] + red_peer[r * 128 + tw], v1 = acc[4 * b + 1] + red_peer[(r + 1) * 128 + tw];
            const float v2 = acc[4 * b + 2] + red_peer[(r + 2) * 128 + tw], v3 = acc[4 * b + 3] + red_peer[(r + 3) * 128 + tw];
            stmatrix_x2(st_addr + b * 16, pack_bf16(v0, v1), pack_bf16(v2, v3));
        }
    }
    named_bar_sync(2 + mh, 256);
#pragma unroll
    for (int it = 0; it < 3; it++) {
        const int idx = it * 256 + kh * 128 + tw;
        if (idx < 64 * 9) {
            const int r = idx / 9, i = idx - r * 9;
            uint4 v = lds128(stg + r * K3_PITCH + i * 16);
            *reinterpret_cast<uint4*>(out + (size_t)(rb * 128 + mh * 64 + r) * D_ + nj * 72 + i * 8) = v;
        }
    }
    asm volatile("barrier.cluster.wait.aligned;" ::: "memory");
}

typedef CUresult (*PFN_encodeTiled)(CUtensorMap*, CUtensorMapDataType, cuuint32_t, void*, const cuuint64_t*, const cuuint64_t*,
                                    const cuuint32_t*, const cuuint32_t*, CUtensorMapInterleave, CUtensorMapSwizzle,
                                    CUtensorMapL2promotion, CUtensorMapFloatOOBfill);

struct Maps {
    CUtensorMap X, WA, WAn, WB, WBn, C, OA, OAn, OB, OBn;
};

void encode2d(PFN_encodeTiled fn, CUtensorMap* m, const void* ptr, uint64_t inner, uint64_t outer, uint32_t box_in,
              uint32_t box_out, CUtensorMapSwizzle swz = CU_TENSOR_MAP_SWIZZLE_128B) {
    cuuint64_t dims[2] = {inner, outer};
    cuuint64_t strides[1] = {inner * 2};
    cuuint32_t box[2] = {box_in, box_out};
    cuuint32_t es[2] = {1, 1};
    fn(m, CU_TENSOR_MAP_DATA_TYPE_BFLOAT16, 2, const_cast<void*>(ptr), dims, strides, box, es, CU_TENSOR_MAP_INTERLEAVE_NONE,
       swz, CU_TENSOR_MAP_L2_PROMOTION_L2_256B, CU_TENSOR_MAP_FLOAT_OOB_FILL_NONE);
}

}

extern "C" void kernel_launch(void* const* d_in, const int* in_sizes, int n_in, void* d_out, int out_size) {
    (void)in_sizes; (void)n_in; (void)out_size;
    const bf16* x = (const bf16*)d_in[0];
    const bf16* wqkvA = (const bf16*)d_in[1];
    const bf16* woA = (const bf16*)d_in[2];
    const bf16* wqkvB = (const bf16*)d_in[4];
    const bf16* woB = (const bf16*)d_in[5];
    const bf16* gate_w = (const bf16*)d_in[6];
    bf16* out = (bf16*)d_out;

    static Maps maps;
    static const void* cached[5] = {nullptr, nullptr, nullptr, nullptr, nullptr};
    static bool attrs_done = false;
    if (!attrs_done) {
        cudaFuncSetAttribute(k1_qkv, cudaFuncAttributeMaxDynamicSharedMemorySize, K1_SMEM);
        cudaFuncSetAttribute(k2_attn, cudaFuncAttributeMaxDynamicSharedMemorySize, K2_SMEM);
        cudaFuncSetAttribute(k3_out, cudaFuncAttributeMaxDynamicSharedMemorySize, K3_SMEM);
        attrs_done = true;
    }
    if (cached[0] != x || cached[1] != wqkvA || cached[2] != woA || cached[3] != wqkvB || cached[4] != woB) {
        void* fnp = nullptr;
        cudaDriverEntryPointQueryResult qres;
        cudaGetDriverEntryPoint("cuTensorMapEncodeTiled", &fnp, cudaEnableDefault, &qres);
        PFN_encodeTiled fn = (PFN_encodeTiled)fnp;
        void* cptr = nullptr;
        cudaGetSymbolAddress(&cptr, g_C);
        encode2d(fn, &maps.X, x, 576, 2048, 64, 128);
        encode2d(fn, &maps.WA, wqkvA, 1728, 576, 64, 64);
        encode2d(fn, &maps.WAn, wqkvA, 1728, 576, 24, 64);
        encode2d(fn, &maps.WB, wqkvB, 1728, 576, 64, 64);
        encode2d(fn, &maps.WBn, wqkvB, 1728, 576, 24, 64);
        {
            cuuint64_t dims[2] = {4608, 256};
            cuuint64_t strides[1] = {18432};
            cuuint32_t box[2] = {256, 8};
            cuuint32_t es[2] = {1, 1};
            fn(&maps.C, CU_TENSOR_MAP_DATA_TYPE_UINT32, 2, cptr, dims, strides, box, es, CU_TENSOR_MAP_INTERLEAVE_NONE,
               CU_TENSOR_MAP_SWIZZLE_NONE, CU_TENSOR_MAP_L2_PROMOTION_L2_256B, CU_TENSOR_MAP_FLOAT_OOB_FILL_NONE);
        }
        encode2d(fn, &maps.OA, woA, 576, 576, 64, 64);
        encode2d(fn, &maps.OAn, woA, 576, 576, 8, 64, CU_TENSOR_MAP_SWIZZLE_NONE);
        encode2d(fn, &maps.OB, woB, 576, 576, 64, 64);
        encode2d(fn, &maps.OBn, woB, 576, 576, 8, 64, CU_TENSOR_MAP_SWIZZLE_NONE);
        cached[0] = x; cached[1] = wqkvA; cached[2] = woA; cached[3] = wqkvB; cached[4] = woB;
    }

    cudaStream_t st = cudaStreamPerThread;
    k1_qkv<<<128, 256, K1_SMEM, st>>>(maps.X, maps.WA, maps.WAn, maps.WB, maps.WBn, x, gate_w);

    cudaLaunchAttribute at[1];
    at[0].id = cudaLaunchAttributeProgrammaticStreamSerialization;
    at[0].val.programmaticStreamSerializationAllowed = 1;
    cudaLaunchConfig_t cfg = {};
    cfg.gridDim = dim3(128);
    cfg.blockDim = dim3(512);
    cfg.stream = st;
    cfg.attrs = at;
    cfg.numAttrs = 1;
    cfg.dynamicSmemBytes = K2_SMEM;
    cfg.gridDim = dim3(132);
    cudaLaunchKernelEx(&cfg, k2_attn, woA, woB);
    cfg.dynamicSmemBytes = K3_SMEM;
    cfg.gridDim = dim3(128);
    cfg.blockDim = dim3(576);
    cudaLaunchKernelEx(&cfg, k3_out, maps.C, maps.OA, maps.OAn, maps.OB, maps.OBn, out);
}
```
